```python
import torch

def _softmax(x, axis=-1):
    return torch.softmax(x, dim=axis)

def _gelu(x):
    return torch.nn.functional.gelu(x, approximate='tanh')

def _silu(x):
    return torch.nn.functional.silu(x)

def _sigmoid(x):
    return torch.sigmoid(x)

def _layernorm(x, axis=-1, eps=1e-05):
    m = x.mean(dim=axis, keepdim=True)
    v = x.var(dim=axis, keepdim=True, unbiased=False)
    return (x - m) / torch.sqrt(v + eps)

def _scatter_add(tgt, idx, src, axis=0):
    return tgt.clone().index_add_(axis, idx, src)

def _segment_sum(src, seg, n):
    out = torch.zeros((n,) + src.shape[1:], dtype=src.dtype)
    return out.index_add_(0, seg, src)

def _pad(x, pw):
    flat = tuple((v for pair in reversed(pw) for v in pair))
    return torch.nn.functional.pad(x, flat)
kernel_name = 'concat_heads__softmax_full_mha__memory_aug_recurrent_mem_tr__prompt'

def setup_inputs():

    _w = lambda a: (lambda t: t.to(torch.bfloat16) if t.is_floating_point() else t)(torch.as_tensor(a))

    def _A_setup():
        B, S, D = (1, 2048, 640)
        return {'x': _w((lambda *s: torch.randn(*s, dtype=torch.bfloat16) * 0.2)(B, S, D)), 'wqkv': _w((lambda *s: torch.randn(*s, dtype=torch.bfloat16) * 0.2)(D, 3 * D)), 'wo': _w((lambda *s: torch.randn(*s, dtype=torch.bfloat16) * 0.05)(D, D))}
    _A_in = _A_setup()

    def _B_setup():
        B, S, Dm = (1, 2048, 640)
        H, Dh = (32, 128)
        M, seg = (8, 32)
        seg = min(seg, S)
        S = S // seg * seg
        return {'x': _w((lambda *s: torch.randn(*s, dtype=torch.bfloat16) * 0.05)(B, S, Dm)), 'mem0': _w((lambda *s: torch.randn(*s, dtype=torch.bfloat16) * 0.8)(B, M, Dm)), 'Wq': _w((lambda *s: torch.randn(*s, dtype=torch.bfloat16) * 1.6)(Dm, H, Dh) * Dm ** (-0.5)), 'Wk': _w((lambda *s: torch.randn(*s, dtype=torch.bfloat16) * 1.6)(Dm, H, Dh) * Dm ** (-0.5)), 'Wv': _w((lambda *s: torch.randn(*s, dtype=torch.bfloat16) * 0.8)(Dm, H, Dh) * Dm ** (-0.5)), 'Wo': _w((lambda *s: torch.randn(*s, dtype=torch.bfloat16) * 0.8)(H, Dh, Dm) * (H * Dh) ** (-0.5)), 'seg_len': seg}
    _B_in = _B_setup()
    return {'A_x': _A_in['x'], 'A_wqkv': _A_in['wqkv'], 'A_wo': _A_in['wo'], 'B_x': _B_in['x'], 'B_mem0': _B_in['mem0'], 'B_Wq': _B_in['Wq'], 'B_Wk': _B_in['Wk'], 'B_Wv': _B_in['Wv'], 'B_Wo': _B_in['Wo'], 'B_seg_len': _B_in['seg_len']}

def reference(A_x, A_wqkv, A_wo, B_x, B_mem0, B_Wq, B_Wk, B_Wv, B_Wo, B_seg_len):

    def _A_ref(x, wqkv, wo):
        B, S, D = x.shape
        H = 32
        Dh = D // H
        qkv = (lambda x, *d: x.permute(*d))((x @ wqkv).reshape(B, S, 3, H, Dh), 2, 0, 3, 1, 4)
        q, k, v = (qkv[0], qkv[1], qkv[2])
        scale = Dh ** (-0.5)
        scores = torch.einsum('bhqd,bhkd->bhqk', q, k) * scale
        p = _softmax(scores, axis=-1)
        o = torch.einsum('bhqk,bhkd->bhqd', p, v)
        return (lambda x, *d: x.permute(*d))(o, 0, 2, 1, 3).reshape(B, S, D) @ wo

    def _B_ref(x, mem0, Wq, Wk, Wv, Wo, seg_len):
        B, S, Dm = x.shape
        H, Dh = (Wq.shape[1], Wq.shape[2])
        M = mem0.shape[1]
        scale = Dh ** (-0.5)
        n_seg = S // seg_len
        L = M + seg_len
        idx = torch.arange(L)
        mask = (idx[:, None] < M) | (idx[:, None] >= idx[None, :])
        mem = mem0
        outs = []
        for s in range(n_seg):
            xs = x[:, s * seg_len:(s + 1) * seg_len, :].clone()
            h = torch.concatenate([mem, xs], axis=1)
            q = torch.einsum('btd,dhe->bhte', h, Wq)
            k = torch.einsum('btd,dhe->bhte', h, Wk)
            v = torch.einsum('btd,dhe->bhte', h, Wv)
            scores = torch.einsum('bhqe,bhke->bhqk', q, k) * scale
            scores = torch.where(mask[None, None], scores, -1000000000.0)
            p = _softmax(scores, axis=-1)
            o = torch.einsum('bhqk,bhke->bhqe', p, v)
            o = torch.einsum('bhte,hed->btd', o, Wo)
            mem = o[:, :M, :].clone()
            outs.append(o[:, M:, :])
        return torch.concatenate(outs, axis=1)
    a = _A_ref(A_x, A_wqkv, A_wo)
    b = _B_ref(B_x, B_mem0, B_Wq, B_Wk, B_Wv, B_Wo, B_seg_len)
    return torch.concatenate([a, b], axis=-1)
```

```cpp
#include <stdio.h>
#include <cuda_runtime.h>
#include <cuda_bf16.h>
#include <cuda.h>
#include <stdint.h>

typedef __nv_bfloat16 bf16;

#define DEVI __device__ __forceinline__

__device__ unsigned int g_err;

DEVI uint32_t smem_u32(const void* p) { return (uint32_t)__cvta_generic_to_shared(p); }
DEVI uint32_t mapa_u32(uint32_t a, uint32_t r) {
    uint32_t o; asm volatile("mapa.shared::cluster.u32 %0, %1, %2;" : "=r"(o) : "r"(a), "r"(r)); return o;
}
DEVI uint32_t pack_bf16(float lo, float hi) {
    uint32_t r; asm("cvt.rn.bf16x2.f32 %0, %1, %2;" : "=r"(r) : "f"(hi), "f"(lo)); return r;
}
DEVI float ex2(float x) { float y; asm("ex2.approx.ftz.f32 %0, %1;" : "=f"(y) : "f"(x)); return y; }
DEVI uint32_t clk32r() { uint32_t t; asm volatile("mov.u32 %0, %%clock;" : "=r"(t) :: "memory"); return t; }
DEVI long long clk64() { long long t; asm volatile("mov.u64 %0, %%clock64;" : "=l"(t) :: "memory"); return t; }

DEVI void mbar_init(uint32_t bar, uint32_t cnt) { asm volatile("mbarrier.init.shared::cta.b64 [%0], %1;" :: "r"(bar), "r"(cnt) : "memory"); }
DEVI void mbar_arrive(uint32_t bar) { asm volatile("mbarrier.arrive.shared::cta.b64 _, [%0];" :: "r"(bar) : "memory"); }
DEVI void mbar_arrive_tx(uint32_t bar, uint32_t tx) { asm volatile("mbarrier.arrive.expect_tx.shared::cta.b64 _, [%0], %1;" :: "r"(bar), "r"(tx) : "memory"); }
DEVI bool mbar_try(uint32_t bar, uint32_t parity) {
    uint32_t ok;
    asm volatile("{\n.reg .pred p;\nmbarrier.try_wait.parity.shared::cta.b64 p, [%1], %2;\nselp.u32 %0, 1, 0, p;\n}"
                 : "=r"(ok) : "r"(bar), "r"(parity) : "memory");
    return ok;
}
DEVI bool mbar_test(uint32_t bar, uint32_t parity) {
    uint32_t ok;
    asm volatile("{\n.reg .pred p;\nmbarrier.test_wait.parity.shared::cta.b64 p, [%1], %2;\nselp.u32 %0, 1, 0, p;\n}"
                 : "=r"(ok) : "r"(bar), "r"(parity) : "memory");
    return ok;
}
DEVI bool mbar_try_cluster(uint32_t bar, uint32_t parity) {
    uint32_t ok;
    asm volatile("{\n.reg .pred p;\nmbarrier.try_wait.parity.acquire.cluster.shared::cta.b64 p, [%1], %2;\nselp.u32 %0, 1, 0, p;\n}"
                 : "=r"(ok) : "r"(bar), "r"(parity) : "memory");
    return ok;
}
#define WAIT_LIMIT (1u << 17)
DEVI void mbar_wait(uint32_t bar, uint32_t parity) {
    uint32_t it = 0;
#pragma unroll 1
    while (!mbar_try(bar, parity)) { if (++it > WAIT_LIMIT) { g_err = 1; break; } }
}
DEVI void bar_sync(int id, int n) { asm volatile("bar.sync %0, %1;" :: "r"(id), "r"(n) : "memory"); }
DEVI void bar_arrive(int id, int n) { asm volatile("bar.arrive %0, %1;" :: "r"(id), "r"(n) : "memory"); }
DEVI void fence_proxy_async() { asm volatile("fence.proxy.async.shared::cta;" ::: "memory"); }
DEVI void cluster_sync() { asm volatile("barrier.cluster.arrive.release.aligned;\nbarrier.cluster.wait.acquire.aligned;" ::: "memory"); }

DEVI void tma_load_2d(uint32_t dst, const CUtensorMap* tm, int c0, int c1, uint32_t bar) {
    asm volatile("cp.async.bulk.tensor.2d.shared::cluster.global.mbarrier::complete_tx::bytes [%0], [%1, {%3, %4}], [%2];"
                 :: "r"(dst), "l"(tm), "r"(bar), "r"(c0), "r"(c1) : "memory");
}
DEVI void tma_load_3d(uint32_t dst, const CUtensorMap* tm, int c0, int c1, int c2, uint32_t bar) {
    asm volatile("cp.async.bulk.tensor.3d.shared::cluster.global.mbarrier::complete_tx::bytes [%0], [%1, {%3, %4, %5}], [%2];"
                 :: "r"(dst), "l"(tm), "r"(bar), "r"(c0), "r"(c1), "r"(c2) : "memory");
}
DEVI void tma_store_2d(const CUtensorMap* tm, uint32_t src, int c0, int c1) {
    asm volatile("cp.async.bulk.tensor.2d.global.shared::cta.bulk_group [%0, {%2, %3}], [%1];"
                 :: "l"(tm), "r"(src), "r"(c0), "r"(c1) : "memory");
}
DEVI void tma_store_3d(const CUtensorMap* tm, uint32_t src, int c0, int c1, int c2) {
    asm volatile("cp.async.bulk.tensor.3d.global.shared::cta.bulk_group [%0, {%2, %3, %4}], [%1];"
                 :: "l"(tm), "r"(src), "r"(c0), "r"(c1), "r"(c2) : "memory");
}
DEVI void bulk_commit() { asm volatile("cp.async.bulk.commit_group;" ::: "memory"); }
template <int N> DEVI void bulk_wait_read() { asm volatile("cp.async.bulk.wait_group.read %0;" :: "n"(N) : "memory"); }
template <int N> DEVI void bulk_wait() { asm volatile("cp.async.bulk.wait_group %0;" :: "n"(N) : "memory"); }
DEVI void bulk_copy_s2s(uint32_t dst_cluster, uint32_t src, uint32_t bytes, uint32_t bar_cluster) {
    asm volatile("cp.async.bulk.shared::cluster.shared::cta.mbarrier::complete_tx::bytes [%0], [%1], %2, [%3];"
                 :: "r"(dst_cluster), "r"(src), "r"(bytes), "r"(bar_cluster) : "memory");
}
DEVI void st_async_b32(uint32_t dst_cluster, uint32_t v, uint32_t bar_cluster) {
    asm volatile("st.async.weak.shared::cluster.mbarrier::complete_tx::bytes.b32 [%0], %1, [%2];"
                 :: "r"(dst_cluster), "r"(v), "r"(bar_cluster) : "memory");
}
DEVI void prefetch_tmap(const CUtensorMap* tm) { asm volatile("prefetch.tensormap [%0];" :: "l"(tm) : "memory"); }

DEVI void ldsm_x4(uint32_t* r, uint32_t a) {
    asm volatile("ldmatrix.sync.aligned.m8n8.x4.shared.b16 {%0,%1,%2,%3}, [%4];" : "=r"(r[0]), "=r"(r[1]), "=r"(r[2]), "=r"(r[3]) : "r"(a) : "memory");
}
DEVI void ldsm_x4_t(uint32_t* r, uint32_t a) {
    asm volatile("ldmatrix.sync.aligned.m8n8.x4.trans.shared.b16 {%0,%1,%2,%3}, [%4];" : "=r"(r[0]), "=r"(r[1]), "=r"(r[2]), "=r"(r[3]) : "r"(a) : "memory");
}
DEVI void ldsm_x2(uint32_t* r, uint32_t a) {
    asm volatile("ldmatrix.sync.aligned.m8n8.x2.shared.b16 {%0,%1}, [%2];" : "=r"(r[0]), "=r"(r[1]) : "r"(a) : "memory");
}
DEVI void ldsm_x2_t(uint32_t* r, uint32_t a) {
    asm volatile("ldmatrix.sync.aligned.m8n8.x2.trans.shared.b16 {%0,%1}, [%2];" : "=r"(r[0]), "=r"(r[1]) : "r"(a) : "memory");
}
DEVI void mma16816(float* c, uint32_t a0, uint32_t a1, uint32_t a2, uint32_t a3, uint32_t b0, uint32_t b1) {
    asm volatile("mma.sync.aligned.m16n8k16.row.col.f32.bf16.bf16.f32 {%0,%1,%2,%3}, {%4,%5,%6,%7}, {%8,%9}, {%0,%1,%2,%3};"
                 : "+f"(c[0]), "+f"(c[1]), "+f"(c[2]), "+f"(c[3]) : "r"(a0), "r"(a1), "r"(a2), "r"(a3), "r"(b0), "r"(b1));
}
DEVI void mma1688(float* c, uint32_t a0, uint32_t a1, uint32_t b0) {
    asm volatile("mma.sync.aligned.m16n8k8.row.col.f32.bf16.bf16.f32 {%0,%1,%2,%3}, {%4,%5}, {%6}, {%0,%1,%2,%3};"
                 : "+f"(c[0]), "+f"(c[1]), "+f"(c[2]), "+f"(c[3]) : "r"(a0), "r"(a1), "r"(b0));
}
DEVI void sts32(uint32_t a, uint32_t v) { asm volatile("st.shared.b32 [%0], %1;" :: "r"(a), "r"(v) : "memory"); }
DEVI void sts64(uint32_t a, uint32_t v0, uint32_t v1) { asm volatile("st.shared.v2.b32 [%0], {%1,%2};" :: "r"(a), "r"(v0), "r"(v1) : "memory"); }
DEVI void sts128(uint32_t a, const uint4& v) { asm volatile("st.shared.v4.b32 [%0], {%1,%2,%3,%4};" :: "r"(a), "r"(v.x), "r"(v.y), "r"(v.z), "r"(v.w) : "memory"); }
DEVI void sts64f(uint32_t a, float v0, float v1) { asm volatile("st.shared.v2.f32 [%0], {%1,%2};" :: "r"(a), "f"(v0), "f"(v1) : "memory"); }
DEVI float2 lds64f(uint32_t a) { float2 v; asm volatile("ld.shared.v2.f32 {%0,%1}, [%2];" : "=f"(v.x), "=f"(v.y) : "r"(a) : "memory"); return v; }
DEVI uint4 lds128(uint32_t a) { uint4 v; asm volatile("ld.shared.v4.b32 {%0,%1,%2,%3}, [%4];" : "=r"(v.x), "=r"(v.y), "=r"(v.z), "=r"(v.w) : "r"(a) : "memory"); return v; }

DEVI void wg_fence() { asm volatile("wgmma.fence.sync.aligned;" ::: "memory"); }
DEVI void wg_commit() { asm volatile("wgmma.commit_group.sync.aligned;" ::: "memory"); }
template <int N> DEVI void wg_wait() { asm volatile("wgmma.wait_group.sync.aligned %0;" :: "n"(N) : "memory"); }
DEVI uint64_t make_desc(uint32_t addr, uint32_t lbo_bytes, uint32_t sbo_bytes, uint32_t swz) {
    return (uint64_t)((addr & 0x3FFFF) >> 4) | ((uint64_t)(lbo_bytes >> 4) << 16) | ((uint64_t)(sbo_bytes >> 4) << 32) | ((uint64_t)swz << 62);
}

DEVI void st_relaxed_v4(void* p, uint32_t a, uint32_t b, uint32_t c, uint32_t d) {
    asm volatile("st.relaxed.gpu.global.v4.u32 [%0], {%1,%2,%3,%4};" :: "l"(p), "r"(a), "r"(b), "r"(c), "r"(d) : "memory");
}
DEVI void st_relaxed_u32(void* p, uint32_t v) { asm volatile("st.relaxed.gpu.global.u32 [%0], %1;" :: "l"(p), "r"(v) : "memory"); }

DEVI uint32_t pin(uint32_t x) { asm volatile("" : "+r"(x)); return x; }
DEVI uint32_t junk() { uint32_t x; asm volatile("" : "=r"(x)); return x; }

#define TL_BEGIN(k)
#define TL_END(k)
namespace chain {

constexpr int NSEG = 64, SEG = 32;
constexpr int NCTA = 96;

constexpr uint32_t S_WO = 0;
constexpr uint32_t S_XT = 65536;
constexpr uint32_t S_KR = S_XT + 40960;
constexpr uint32_t S_VR = S_KR + 24576;
constexpr uint32_t S_QR = S_VR + 24576;
constexpr uint32_t S_MEMB = S_QR + 24576;
constexpr uint32_t S_QKVM = S_MEMB + 10240;
constexpr uint32_t S_SBUF = S_QKVM + 12288;
constexpr uint32_t S_OB = S_SBUF + 1536;
constexpr uint32_t S_RED = S_OB + 2048;
constexpr uint32_t S_OST = S_RED + 1024;
constexpr uint32_t S_END = S_OST + 8704;
constexpr uint32_t S_WST = 65536;
constexpr uint32_t S_BARS = S_WST + 163840;
constexpr uint32_t SMEM_BYTES = S_BARS + 256;
static_assert(S_END <= S_BARS, "smem map");
constexpr uint32_t B_W = 0, B_WO = 8, B_X = 16, B_D1 = 24  , B_KV = 40  , B_X0 = 64, B_AD = 80;

#define WREGS 224
#define AREGS 56
#define MEM_POLY 0
#define WPRE 2
#define G2REP 4
constexpr int NSLOT = 4, G2R = G2REP;
constexpr uint32_t SENT = 0u;

__device__ uint4 g1[NSLOT][40][32][32];
__device__ uint32_t g2[NSLOT][G2R][2560];
#define TSTAMP(i)
#define TSTAMP_AUX(i)

DEVI void wgmma_rs_n32(float* d, const uint32_t* a, uint64_t db, int scale_d) {
    asm volatile("{\n.reg .pred p;\nsetp.ne.b32 p, %21, 0;\n"
                 "wgmma.mma_async.sync.aligned.m64n32k16.f32.bf16.bf16 "
                 "{%0,%1,%2,%3,%4,%5,%6,%7,%8,%9,%10,%11,%12,%13,%14,%15}, {%16,%17,%18,%19}, %20, p, 1, 1, 0;\n}"
                 : "+f"(d[0]), "+f"(d[1]), "+f"(d[2]), "+f"(d[3]), "+f"(d[4]), "+f"(d[5]), "+f"(d[6]), "+f"(d[7]),
                   "+f"(d[8]), "+f"(d[9]), "+f"(d[10]), "+f"(d[11]), "+f"(d[12]), "+f"(d[13]), "+f"(d[14]), "+f"(d[15])
                 : "r"(a[0]), "r"(a[1]), "r"(a[2]), "r"(a[3]), "l"(db), "r"(scale_d));
}

DEVI void ld_poll3(uint4* v, const uint4* p0, const uint4* p1, const uint4* p2) {
    asm volatile(
        "ld.relaxed.gpu.global.v4.u32 {%0,%1,%2,%3}, [%12];\n"
        "ld.relaxed.gpu.global.v4.u32 {%4,%5,%6,%7}, [%13];\n"
        "ld.relaxed.gpu.global.v4.u32 {%8,%9,%10,%11}, [%14];\n"
        : "=r"(v[0].x), "=r"(v[0].y), "=r"(v[0].z), "=r"(v[0].w), "=r"(v[1].x), "=r"(v[1].y), "=r"(v[1].z), "=r"(v[1].w),
          "=r"(v[2].x), "=r"(v[2].y), "=r"(v[2].z), "=r"(v[2].w)
        : "l"(p0), "l"(p1), "l"(p2) : "memory");
}
DEVI void ld_poll4(uint4* v, const uint4* p) {
    asm volatile(
        "ld.relaxed.gpu.global.v4.u32 {%0,%1,%2,%3}, [%16];\n"
        "ld.relaxed.gpu.global.v4.u32 {%4,%5,%6,%7}, [%16+512];\n"
        "ld.relaxed.gpu.global.v4.u32 {%8,%9,%10,%11}, [%16+1024];\n"
        "ld.relaxed.gpu.global.v4.u32 {%12,%13,%14,%15}, [%16+1536];\n"
        : "=r"(v[0].x), "=r"(v[0].y), "=r"(v[0].z), "=r"(v[0].w), "=r"(v[1].x), "=r"(v[1].y), "=r"(v[1].z), "=r"(v[1].w),
          "=r"(v[2].x), "=r"(v[2].y), "=r"(v[2].z), "=r"(v[2].w), "=r"(v[3].x), "=r"(v[3].y), "=r"(v[3].z), "=r"(v[3].w)
        : "l"(p) : "memory");
}
DEVI uint32_t or3(uint32_t a, uint32_t b, uint32_t c) { uint32_t r; asm("lop3.b32 %0, %1, %2, %3, 0xFE;" : "=r"(r) : "r"(a), "r"(b), "r"(c)); return r; }
DEVI uint32_t and3(uint32_t a, uint32_t b, uint32_t c) { uint32_t r; asm("lop3.b32 %0, %1, %2, %3, 0x80;" : "=r"(r) : "r"(a), "r"(b), "r"(c)); return r; }
DEVI uint32_t tag_mismatch(const uint4 (&v)[4], uint32_t ph) {
    if (ph) return ~and3(and3(and3(v[0].x, v[0].y, v[0].z), and3(v[0].w, v[1].x, v[1].y), and3(v[1].z, v[1].w, v[2].x)),
                         and3(and3(v[2].y, v[2].z, v[2].w), and3(v[3].x, v[3].y, v[3].z), v[3].w), 0xFFFFFFFFu);
    return or3(or3(or3(v[0].x, v[0].y, v[0].z), or3(v[0].w, v[1].x, v[1].y), or3(v[1].z, v[1].w, v[2].x)),
               or3(or3(v[2].y, v[2].z, v[2].w), or3(v[3].x, v[3].y, v[3].z), v[3].w), 0u);
}
template <class T> DEVI T* pin_ptr(T* p) { asm volatile("" : "+l"(p)); return p; }
DEVI bool any_sent(const uint4& v) { return (v.x == SENT) | (v.w == SENT) | (v.y == SENT) | (v.z == SENT); }
DEVI uint32_t phase_bits(const uint4& v, uint32_t ph) { return (v.x ^ ph) | (v.y ^ ph) | (v.z ^ ph) | (v.w ^ ph); }

constexpr float SCALE_LOG2E = 0.08838834764831845f * 1.4426950408889634f;

DEVI void token_issue(float (&acc)[16], const uint32_t (&a)[160], uint32_t xaddr) {
    const uint64_t d0 = make_desc(xaddr, 16, 1024, 1);
    wg_fence();
#pragma unroll
    for (int j = 0; j < 40; j++)
        wgmma_rs_n32(acc, &a[4 * j], d0 + (uint64_t)(((j >> 2) * 4096 + (j & 3) * 32) >> 4), j > 0);
    wg_commit();
}
DEVI void token_finish(float (&acc)[16], uint32_t dst) {
    wg_wait<0>();
#pragma unroll
    for (int i = 0; i < 16; i++) asm volatile("" : "+f"(acc[i]) :: "memory");
#pragma unroll
    for (int nb = 0; nb < 4; nb++) {
        sts32(dst + nb * 2048, pack_bf16(acc[4 * nb + 0], acc[4 * nb + 1]));
        sts32(dst + nb * 2048 + 128, pack_bf16(acc[4 * nb + 2], acc[4 * nb + 3]));
    }
    fence_proxy_async();
}
DEVI void spin_until(uint32_t t0, uint32_t d) { while (clk32r() - t0 < d) { } }
DEVI float ex2_fma(float x) {
    x = fmaxf(x, -126.0f);
    const float t = x + 12582912.0f;
    const float r = x - (t - 12582912.0f);
    float p = fmaf(r, 0.009618129f, 0.055504109f);
    p = fmaf(p, r, 0.240226507f);
    p = fmaf(p, r, 0.693147181f);
    p = fmaf(p, r, 1.0f);
    return __uint_as_float(__float_as_uint(p) + (__float_as_uint(t) << 23));
}
DEVI float rcp_approx(float x) { float y; asm("rcp.approx.ftz.f32 %0, %1;" : "=f"(y) : "f"(x)); return y; }

template <int NTILE>
DEVI void out_proj(uint32_t aA, uint32_t obAddr, uint4* dstA, uint32_t ph, uint32_t (&w)[WPRE + 1][4]) {
    uint32_t ob[16];
#pragma unroll
    for (int i = 0; i < 4; i++) { const uint4 t = lds128(obAddr + i * 512); ob[4 * i] = t.x; ob[4 * i + 1] = t.y; ob[4 * i + 2] = t.z; ob[4 * i + 3] = t.w; }
    constexpr int NU = 8 * NTILE;
    float e[2][4];
#pragma unroll
    for (int u = 0; u < NU; u++) {
        const int ks = u & 7;
        if (ks == 0) { e[0][0] = e[0][1] = e[0][2] = e[0][3] = 0.f; e[1][0] = e[1][1] = e[1][2] = e[1][3] = 0.f; }
        if (u + WPRE < NU) { ldsm_x4_t(w[(u + WPRE) % (WPRE + 1)], aA + ((u + WPRE) >> 3) * 32768 + ((u + WPRE) & 7) * 2048); __syncwarp(); }
        mma16816(e[u & 1], w[u % (WPRE + 1)][0], w[u % (WPRE + 1)][1], w[u % (WPRE + 1)][2], w[u % (WPRE + 1)][3], ob[2 * ks], ob[2 * ks + 1]);
        if (ks == 7)
            st_relaxed_v4(dstA + (u >> 3) * (8 * 32 * 32),
                          (__float_as_uint(e[0][0] + e[1][0]) & ~1u) | ph, (__float_as_uint(e[0][1] + e[1][1]) & ~1u) | ph,
                          (__float_as_uint(e[0][2] + e[1][2]) & ~1u) | ph, (__float_as_uint(e[0][3] + e[1][3]) & ~1u) | ph);
    }
}

DEVI void store_o_tile(bf16* Og, uint32_t sb, uint32_t at16, int h, int seg, int i) {
    const uint32_t r = (at16 >> 8) + 8 * i, c16 = (at16 >> 4) & 15;
    *reinterpret_cast<uint4*>(Og + (size_t)(seg * SEG + r) * 4096 + h * 128 + c16 * 8) = lds128(sb + S_OST + r * 272 + c16 * 16);
}
DEVI void publish_o(bf16* Og, uint32_t sb, uint32_t at16, int h, int seg) {
#pragma unroll
    for (int i = 0; i < 4; i++) store_o_tile(Og, sb, at16, h, seg, i);
}
template <int MT>
DEVI void token_attn(uint32_t A16, uint32_t AQ, uint32_t AV1, uint32_t AV2, uint32_t AO, uint32_t qo, uint32_t ro, int dh, int lane,
                     uint32_t pause_bar, uint32_t pause_par) {
    constexpr int NJ = MT == 0 ? 3 : 5;
    float sc[NJ][4];
#pragma unroll
    for (int j = 0; j < NJ; j++) { sc[j][0] = sc[j][1] = sc[j][2] = sc[j][3] = 0.f; }
    {
        const uint32_t qaddr = AQ + S_QR + ro + MT * 4096;
        const uint32_t k16 = A16 - ((lane >> 4) << 8);
        uint32_t k[2][NJ][2], q[2][4];
        ldsm_x4_t(q[0], qaddr);
#pragma unroll
        for (int j = 0; j < NJ; j++) ldsm_x2_t(k[0][j], j == 0 ? k16 + qo + 2048 : k16 + S_KR + ro + (j - 1) * 2048);
#pragma unroll
        for (int ks = 0; ks < 8; ks++) {
            if (ks + 1 < 8) {
                ldsm_x4_t(q[(ks + 1) & 1], qaddr + (ks + 1) * 256);
#pragma unroll
                for (int j = 0; j < NJ; j++) ldsm_x2_t(k[(ks + 1) & 1][j], (j == 0 ? k16 + qo + 2048 : k16 + S_KR + ro + (j - 1) * 2048) + (ks + 1) * 256);
            }
            __syncwarp();
#pragma unroll
            for (int j = 0; j < NJ; j++) mma16816(sc[j], q[ks & 1][0], q[ks & 1][1], q[ks & 1][2], q[ks & 1][3], k[ks & 1][j][0], k[ks & 1][j][1]);
        }
    }
    const int t0 = 16 * MT + (lane >> 2), t1 = t0 + 8;
    float m0 = -INFINITY, m1 = -INFINITY;
#pragma unroll
    for (int j = 0; j < NJ; j++) {
        const int kk = 8 * (j - 1) + 2 * (lane & 3);
        if (j > 0 && 8 * j - 1 > 16 * MT) {
            if (kk > t0) sc[j][0] = -INFINITY;
            if (kk + 1 > t0) sc[j][1] = -INFINITY;
            if (kk > t1) sc[j][2] = -INFINITY;
            if (kk + 1 > t1) sc[j][3] = -INFINITY;
        }
        m0 = fmaxf(m0, fmaxf(sc[j][0], sc[j][1]));
        m1 = fmaxf(m1, fmaxf(sc[j][2], sc[j][3]));
    }
    m0 = fmaxf(m0, __shfl_xor_sync(0xffffffffu, m0, 1)); m1 = fmaxf(m1, __shfl_xor_sync(0xffffffffu, m1, 1));
    m0 = fmaxf(m0, __shfl_xor_sync(0xffffffffu, m0, 2)); m1 = fmaxf(m1, __shfl_xor_sync(0xffffffffu, m1, 2));
    const float mc0 = m0 * SCALE_LOG2E, mc1 = m1 * SCALE_LOG2E;
    float s0 = 0.f, s1 = 0.f;
    uint32_t pA[NJ], pB[NJ];
#pragma unroll
    for (int j = 0; j < NJ; j++) {
        const float e0 = ex2(fmaf(sc[j][0], SCALE_LOG2E, -mc0)), e1 = ex2(fmaf(sc[j][1], SCALE_LOG2E, -mc0));
        const float e2 = ex2(fmaf(sc[j][2], SCALE_LOG2E, -mc1)), e3 = ex2(fmaf(sc[j][3], SCALE_LOG2E, -mc1));
        s0 += e0 + e1; s1 += e2 + e3;
        pA[j] = pack_bf16(e0, e1); pB[j] = pack_bf16(e2, e3);
    }
    s0 += __shfl_xor_sync(0xffffffffu, s0, 1); s1 += __shfl_xor_sync(0xffffffffu, s1, 1);
    s0 += __shfl_xor_sync(0xffffffffu, s0, 2); s1 += __shfl_xor_sync(0xffffffffu, s1, 2);
    const float i0 = rcp_approx(s0), i1 = rcp_approx(s1);
    if (pause_bar) mbar_wait(pause_bar, pause_par);
    uint32_t vm[2][2], va[2][4], vb[2][4];
    ldsm_x2(vm[0], AV1 + qo + 4096);
    if (MT == 0) ldsm_x4(va[0], AV1 + S_VR + ro);
    else { ldsm_x4(va[0], AV1 + S_VR + ro + ((lane >> 4) ? 2 * 2048 : 0)); ldsm_x4(vb[0], AV2 + S_VR + ro + 2048); }
#pragma unroll
    for (int np = 0; np < 4; np++) {
        const int c = np & 1, n = c ^ 1;
        if (np < 3) {
            ldsm_x2(vm[n], AV1 + qo + 4096 + (np + 1) * 256);
            if (MT == 0) ldsm_x4(va[n], AV1 + S_VR + ro + (np + 1) * 256);
            else { ldsm_x4(va[n], AV1 + S_VR + ro + ((lane >> 4) ? 2 * 2048 : 0) + (np + 1) * 256); ldsm_x4(vb[n], AV2 + S_VR + ro + 2048 + (np + 1) * 256); }
        }
        __syncwarp();
        float o0[4] = {0.f, 0.f, 0.f, 0.f}, o1[4] = {0.f, 0.f, 0.f, 0.f};
        mma16816(o0, pA[0], pB[0], pA[1], pB[1], vm[c][0], va[c][0]);
        mma16816(o1, pA[0], pB[0], pA[1], pB[1], vm[c][1], va[c][1]);
        if (MT == 0) {
            mma1688(o0, pA[2], pB[2], va[c][2]);
            mma1688(o1, pA[2], pB[2], va[c][3]);
        } else {
            mma16816(o0, pA[2], pB[2], pA[3], pB[3], vb[c][0], vb[c][1]);
            mma16816(o1, pA[2], pB[2], pA[3], pB[3], vb[c][2], vb[c][3]);
            mma1688(o0, pA[NJ - 1], pB[NJ - 1], va[c][2]);
            mma1688(o1, pA[NJ - 1], pB[NJ - 1], va[c][3]);
        }
        const uint32_t st = AO + np * 32;
        sts32(st, pack_bf16(o0[0] * i0, o0[1] * i0));
        sts32(st + 16, pack_bf16(o1[0] * i0, o1[1] * i0));
        sts32(st + 8 * 272, pack_bf16(o0[2] * i1, o0[3] * i1));
        sts32(st + 8 * 272 + 16, pack_bf16(o1[2] * i1, o1[3] * i1));
    }
}

__global__ void __launch_bounds__(384, 1)
chain_kernel(const __grid_constant__ CUtensorMap tmWq, const __grid_constant__ CUtensorMap tmWk,
             const __grid_constant__ CUtensorMap tmWv, const __grid_constant__ CUtensorMap tmWo,
             const __grid_constant__ CUtensorMap tmX, const bf16* __restrict__ mem0, bf16* __restrict__ Og,
             const uint32_t delay1, const uint32_t delay2) {
    extern __shared__ __align__(1024) uint8_t smem_raw[];
    const uint32_t sb = smem_u32(smem_raw);
    const int tid = threadIdx.x, lane = tid & 31;
    const int warp = __shfl_sync(0xffffffffu, tid >> 5, 0);
    uint32_t role; asm("mov.u32 %0, %%cluster_ctarank;" : "=r"(role));
    const int h = blockIdx.x / 3;
    const uint32_t bars = sb + S_BARS;
    TL_BEGIN(0);
    const int T0 = role == 0 ? 0 : (role == 1 ? 14 : 27);
    const int NT = role == 0 ? 14 : 13;

    if (tid == 32) { prefetch_tmap(&tmWo); prefetch_tmap(&tmX); }
    if (tid == 0) {
        mbar_init(bars + B_W, 1); mbar_init(bars + B_WO, 1); mbar_init(bars + B_X, 1);
        mbar_init(bars + B_D1, 8); mbar_init(bars + B_D1 + 8, 8);
        for (int i = 0; i < 3; i++) mbar_init(bars + B_KV + 8 * i, 1);
        mbar_init(bars + B_X0, 1); mbar_init(bars + B_AD, 8);
        asm volatile("fence.mbarrier_init.release.cluster;" ::: "memory");
        const CUtensorMap* tw = role == 0 ? &tmWq : (role == 1 ? &tmWk : &tmWv);
        mbar_arrive_tx(bars + B_W, 163840);
        for (int i = 0; i < 10; i++) tma_load_2d(sb + S_WST + i * 16384, tw, h * 128 + (i & 1) * 64, (i >> 1) * 128, bars + B_W);
        mbar_arrive_tx(bars + B_X0, 40960);
        tma_load_3d(sb + S_WO, &tmX, 0, 0, 0, bars + B_X0);
        if (blockIdx.x < NSEG)
            asm volatile("cp.async.bulk.prefetch.tensor.3d.L2.global [%0, {%1, %2, %3}];" :: "l"(&tmX), "r"(0), "r"((int)blockIdx.x * SEG), "r"(0) : "memory");
    }
    __syncthreads();
    cluster_sync();

    if (warp < 8) {
        asm volatile("setmaxnreg.inc.sync.aligned.u32 %0;" :: "n"(WREGS));
        uint32_t a[160];
        mbar_wait(bars + B_W, 0);
        {
            const int mi = lane >> 3, row = lane & 7;
            const int col = 16 * warp + (mi & 1) * 8;
            const uint32_t base = sb + S_WST + (col >> 6) * 16384;
            const uint32_t ch = (col & 63) >> 3;
#pragma unroll
            for (int j = 0; j < 40; j++) {
                const int k = 16 * j + (mi >> 1) * 8 + row;
                const uint32_t addr = base + (k >> 7) * 32768 + (k & 127) * 128 + ((ch ^ (k & 7)) << 4);
                ldsm_x4_t(&a[4 * j], addr);
            }
        }
        cluster_sync();
        const uint32_t ringMine = sb + (role == 0 ? S_QR : (role == 1 ? S_KR : S_VR));
        const uint32_t peerA = role == 0 ? 1 : 0, peerB = role == 2 ? 1 : 2;
        const uint32_t kvBytes = role == 0 ? 16384 : 8192;
        uint32_t xph = 0;
        const int mi = lane >> 3, row = lane & 7;
        const uint32_t L16 = pin(sb + lane * 16);
        const uint32_t LQ = pin(sb + (lane >> 2) * 16 + (lane & 3) * 4);
        const uint32_t LV1 = pin(sb + ((mi & 1) * 8 + row + 16 * warp) * 16 + (mi >> 1) * 6144);
        const uint32_t LV2 = pin(sb + ((mi >> 1) * 8 + row + 16 * warp) * 16 + (1 + (mi & 1)) * 2048);
        const uint32_t LS = pin(sb + S_SBUF + ((lane >> 2) * 40 + (lane & 3) * 2) * 4);
        const uint32_t aA = pin(sb + S_WO + (warp >> 2) * 16384 + ((mi >> 1) * 8 + row) * 128 + (((2 * (warp & 3) + (mi & 1)) ^ row) << 4));
        const uint32_t ringOff = ringMine - sb;
        const uint32_t rA = mapa_u32(sb, peerA) - sb, rB = mapa_u32(sb, peerB) - sb;
        const bool two = warp + 8 < NT;
        uint4* const g1base = &g1[0][T0 + warp][h][lane];
        uint32_t s3 = 0;
        uint32_t kvbits = 0;

        for (int s = -2; s < NSEG; s++) {
            const uint32_t slot = s & (NSLOT - 1);
            uint32_t tpub = 0;
            if (s >= 0) {
                const uint32_t par = s & 1;
                TSTAMP(0);
                uint32_t p0, p1;
                {
                    float c[4][4];
#pragma unroll
                    for (int i = 0; i < 4; i++) { c[i][0] = c[i][1] = c[i][2] = c[i][3] = 0.f; }
                    const uint32_t mb = L16 + S_MEMB;
                    uint32_t b[3][4];
                    ldsm_x4_t(b[0], mb);
                    ldsm_x4_t(b[1], mb + 512);
#pragma unroll
                    for (int jj = 0; jj < 20; jj++) {
                        if (jj + 2 < 20) { ldsm_x4_t(b[(jj + 2) % 3], mb + (jj + 2) * 512); __syncwarp(); }
                        mma16816(c[(2 * jj) & 3], a[8 * jj + 0], a[8 * jj + 1], a[8 * jj + 2], a[8 * jj + 3], b[jj % 3][0], b[jj % 3][1]);
                        mma16816(c[(2 * jj + 1) & 3], a[8 * jj + 4], a[8 * jj + 5], a[8 * jj + 6], a[8 * jj + 7], b[jj % 3][2], b[jj % 3][3]);
                    }
                    p0 = pack_bf16((c[0][0] + c[1][0]) + (c[2][0] + c[3][0]), (c[0][1] + c[1][1]) + (c[2][1] + c[3][1]));
                    p1 = pack_bf16((c[0][2] + c[1][2]) + (c[2][2] + c[3][2]), (c[0][3] + c[1][3]) + (c[2][3] + c[3][3]));
                }
                {
                    const uint32_t off = LQ + S_QKVM + role * 2048 + par * 6144 + (role == 0 ? (warp >> 1) * 512 + (warp & 1) * 128 : warp * 256);
                    const uint32_t off1 = off + (role == 0 ? 256 : 128);
                    const uint32_t bo = bars + B_D1 + par * 8;
                    st_async_b32(rA + off, p0, rA + bo); st_async_b32(rB + off, p0, rB + bo);
                    st_async_b32(rA + off1, p1, rA + bo); st_async_b32(rB + off1, p1, rB + bo);
                    sts32(off, p0); sts32(off1, p1);
                    __syncwarp();
                    if (lane == 0) {
                        if (warp == 0) mbar_arrive_tx(bo, 4096); else mbar_arrive(bo);
                        if (s > 0) mbar_arrive(bars + B_AD);
                    }
                }
                TSTAMP(1);
                const uint32_t ph = ((s >> 2) & 1) ^ 1;
                if (s + 1 < NSEG) {
                    mbar_wait(bars + B_KV + s3 * 8, (kvbits >> s3) & 1);
                    const uint32_t ro = s3 * 8192, qo = S_QKVM + par * 6144;
                    uint32_t kf[16], vb[10];
                    if (warp >= 1 && warp < 5) {
#pragma unroll
                        for (int jj = 0; jj < 4; jj++) ldsm_x4_t(&kf[4 * jj], L16 + S_KR + ro + (warp - 1) * 2048 + jj * 512);
                    }
                    mbar_wait(bars + B_D1 + par * 8, (s >> 1) & 1);
                    TSTAMP(2);
                    if (warp < 5) {
                        if (warp == 0) {
#pragma unroll
                            for (int jj = 0; jj < 4; jj++) ldsm_x4_t(&kf[4 * jj], L16 + qo + 2048 + jj * 512);
                        }
                        uint32_t q[3][4];
                        const uint32_t qswz = L16 + qo;
                        ldsm_x4_t(q[0], qswz);
                        ldsm_x4_t(q[1], qswz + 512);
                        float sA[4] = {0.f, 0.f, 0.f, 0.f}, sB[4] = {0.f, 0.f, 0.f, 0.f};
#pragma unroll
                        for (int jj = 0; jj < 4; jj++) {
                            if (jj + 2 < 4) { ldsm_x4_t(q[(jj + 2) % 3], qswz + (jj + 2) * 512); __syncwarp(); }
                            mma16816(sA, q[jj % 3][0], q[jj % 3][1], q[jj % 3][2], q[jj % 3][3], kf[4 * jj], kf[4 * jj + 1]);
                            mma16816(sB, q[jj % 3][0], q[jj % 3][1], q[jj % 3][2], q[jj % 3][3], kf[4 * jj + 2], kf[4 * jj + 3]);
                        }
                        sts64f(LS + warp * 32, sA[0] + sB[2], sA[1] + sB[3]);
                    }
                    ldsm_x4(&vb[0], LV1 + S_VR + ro);
                    ldsm_x4(&vb[4], LV2 + S_VR + ro);
                    ldsm_x2(&vb[8], LV1 + qo + 4096);
                    uint32_t w[WPRE + 1][4];
                    if (s == 0) mbar_wait(bars + B_WO, 0);
#pragma unroll
                    for (int i = 0; i < WPRE; i++) ldsm_x4_t(w[i], aA + i * 2048);
                    bar_sync(1, 256);
                    TSTAMP(3);
                    uint32_t pa[5]; float inv;
                    {
                        float sv[10];
#pragma unroll
                        for (int j = 0; j < 5; j++) {
                            const float2 t = lds64f(LS + j * 32);
                            sv[2 * j] = t.x; sv[2 * j + 1] = t.y;
                        }
                        float m = fmaxf(fmaxf(fmaxf(sv[0], sv[1]), fmaxf(sv[2], sv[3])), fmaxf(fmaxf(sv[4], sv[5]), fmaxf(sv[6], sv[7])));
                        m = fmaxf(m, fmaxf(sv[8], sv[9]));
                        m = fmaxf(m, __shfl_xor_sync(0xffffffffu, m, 1));
                        m = fmaxf(m, __shfl_xor_sync(0xffffffffu, m, 2));
                        const float mc = m * SCALE_LOG2E;
#pragma unroll
                        for (int j = 0; j < 10; j++) { const float xx = fmaf(sv[j], SCALE_LOG2E, -mc); sv[j] = j < MEM_POLY ? ex2_fma(xx) : ex2(xx); }
#pragma unroll
                        for (int j = 0; j < 5; j++) pa[j] = pack_bf16(sv[2 * j], sv[2 * j + 1]);
                        float sum = (((sv[0] + sv[1]) + (sv[2] + sv[3])) + ((sv[4] + sv[5]) + (sv[6] + sv[7]))) + (sv[8] + sv[9]);
                        sum += __shfl_xor_sync(0xffffffffu, sum, 1);
                        sum += __shfl_xor_sync(0xffffffffu, sum, 2);
                        inv = rcp_approx(sum);
                    }
                    {
                        float o0[4] = {0.f, 0.f, 0.f, 0.f}, o1[4] = {0.f, 0.f, 0.f, 0.f};
                        const uint32_t j0 = junk(), j1 = junk();
                        mma16816(o0, pa[0], j0, pa[1], j1, vb[8], vb[0]);
                        mma16816(o1, pa[0], j0, pa[1], j1, vb[9], vb[1]);
                        const uint32_t j2 = junk(), j3 = junk();
                        mma16816(o0, pa[2], j2, pa[3], j3, vb[4], vb[5]);
                        mma16816(o1, pa[2], j2, pa[3], j3, vb[6], vb[7]);
                        const uint32_t j4 = junk();
                        mma1688(o0, pa[4], j4, vb[2]);
                        mma1688(o1, pa[4], j4, vb[3]);
                        sts64(L16 + S_OB + (warp >> 1) * 512 + (warp & 1) * 8,
                              pack_bf16(o0[0] * inv, o0[1] * inv), pack_bf16(o1[0] * inv, o1[1] * inv));
                    }
                    bar_sync(1, 256);
                    TSTAMP(4);
                    uint4* dst = g1base + slot * (40 * 32 * 32);
                    if (two) out_proj<2>(aA, L16 + S_OB, dst, ph, w);
                    else     out_proj<1>(aA, L16 + S_OB, dst, ph, w);
                    kvbits ^= 1u << s3;
                } else {
                    mbar_wait(bars + B_D1 + par * 8, (s >> 1) & 1);
                    uint4* dst = g1base + slot * (40 * 32 * 32);
                    st_relaxed_v4(dst, ph, ph, ph, ph);
                    if (two) st_relaxed_v4(dst + 8 * 32 * 32, ph, ph, ph, ph);
                }
                tpub = clk32r();
                TSTAMP(5);
                bar_sync(2, 384);
            }
            uint4 v[3];
            const bool poll = s >= 0 && s + 1 < NSEG;
            const uint32_t t16 = pin(threadIdx.x) * 16;
            const uint4* src = reinterpret_cast<const uint4*>(reinterpret_cast<const char*>(&g2[slot][blockIdx.x & (G2R - 1)][0]) + t16);
            const uint4* src3 = src + (t16 < 2048 ? 512 : 0);
            if (s + 2 < NSEG) {
                float acc[16];
                if (s == -2) mbar_wait(bars + B_X0, 0); else { mbar_wait(bars + B_X, xph); xph ^= 1; }
                token_issue(acc, a, sb + (s == -2 ? S_WO : S_XT));
                if (poll) spin_until(tpub, delay2);
                ld_poll3(v, src, src + 256, src3);
                __syncwarp();
                const uint32_t s3n = s < 0 ? s + 2 : (s3 == 0 ? 2 : s3 - 1);
                token_finish(acc, LQ + ringOff + warp * 256 + s3n * 8192);
            } else {
                if (poll) spin_until(tpub, delay2);
                ld_poll3(v, src, src + 256, src3);
            }
            TSTAMP(6);
            if (s < 0) {
                bar_sync(1, 256);
                if (tid == 0) {
                    if (s == -2) {
                        mbar_arrive_tx(bars + B_WO, 65536);
                        for (int i = 0; i < 4; i++) tma_load_2d(sb + S_WO + i * 16384, &tmWo, T0 * 16 + i * 64, h * 128, bars + B_WO);
                        mbar_arrive_tx(bars + B_KV, kvBytes);
                        if (role != 0) {
                            bulk_copy_s2s(rA + ringMine, ringMine, 8192, rA + bars + B_KV);
                            bulk_copy_s2s(rB + ringMine, ringMine, 8192, rB + bars + B_KV);
                        }
                    } else {
                        mbar_arrive_tx(bars + B_X, 40960);
                        tma_load_3d(sb + S_XT, &tmX, 0, 2 * SEG, 0, bars + B_X);
                    }
                }
                if (s == -1) bar_sync(5, 384);
                continue;
            }
            if (poll) {
                uint32_t it = 0;
#pragma unroll 1
                while (any_sent(v[0]) | any_sent(v[1]) | any_sent(v[2])) {
                    ld_poll3(v, src, src + 256, src3);
                    if (++it > WAIT_LIMIT) { g_err = 3; break; }
                }
                sts128(sb + S_MEMB + t16, v[0]);
                sts128(sb + S_MEMB + t16 + 4096, v[1]);
                if (t16 < 2048) sts128(sb + S_MEMB + t16 + 8192, v[2]);
                bar_sync(1, 256);
                if (tid == 0 && s + 3 < NSEG) {
                    mbar_arrive_tx(bars + B_X, 40960);
                    tma_load_3d(sb + S_XT, &tmX, 0, (s + 3) * SEG, 0, bars + B_X);
                }
            }
            TSTAMP(7);
            if (s == NSEG - 2) asm volatile("griddepcontrol.launch_dependents;");
            s3 = s3 == 2 ? 0 : s3 + 1;
        }
        TL_END(0);
        cluster_sync();
    } else {
        asm volatile("setmaxnreg.dec.sync.aligned.u32 %0;" :: "n"(AREGS));
        const int aw = warp - 8;
        const int cta = role * 32 + h;
        const bool owner = cta < 80;
        uint4 m0[5];
#pragma unroll
        for (int i = 0; i < 5; i++) { const int e = tid - 256 + 128 * i; m0[i] = *reinterpret_cast<const uint4*>(mem0 + (e / 80) * 640 + (e % 80) * 8); }
        cluster_sync();
        if (tid == 256) {
            fence_proxy_async();
            mbar_arrive_tx(bars + B_X, 40960);
            tma_load_3d(sb + S_XT, &tmX, 0, SEG, 0, bars + B_X);
            for (int i = 0; i < 4; i++)
                asm volatile("cp.async.bulk.prefetch.tensor.2d.L2.global [%0, {%1, %2}];" :: "l"(&tmWo), "r"(T0 * 16 + i * 64), "r"(h * 128) : "memory");
        }
        __syncwarp();
#pragma unroll
        for (int i = 0; i < 5; i++) {
            const int e = tid - 256 + 128 * i, r = e / 80, c8 = e % 80;
            const uint32_t w[4] = {m0[i].x, m0[i].y, m0[i].z, m0[i].w};
#pragma unroll
            for (int k = 0; k < 8; k++) {
                const uint16_t x = (uint16_t)(w[k >> 1] >> ((k & 1) * 16));
                asm volatile("st.shared.u16 [%0], %1;" :: "r"(sb + S_MEMB + (c8 * 8 + k) * 16 + r * 2), "h"(x) : "memory");
            }
        }
        bar_arrive(5, 384);
        const int oword = ((cta >> 1) * 16 + (((cta & 1) * 16 + (lane & 15)) >> 2) + (lane >> 4) * 8) * 4 + (lane & 3);
        if (owner) for (int r = aw; r < G2R; r += 4) { st_relaxed_u32(&g2[1][r][oword], SENT); st_relaxed_u32(&g2[2][r][oword], SENT); }
        for (int s = 0; s < NSEG; s++) {
            if (s == NSEG - 1) asm volatile("griddepcontrol.launch_dependents;");
            const uint32_t at16 = pin((pin(threadIdx.x) - 256) * 16);
            const uint32_t ln0 = (at16 >> 4) & 31;
            const uint32_t o1 = (((cta >> 1) % 40) * 32 * 32 + (aw * 8 + (ln0 >> 4) * 4) * 32 + (cta & 1) * 16 + (ln0 & 15)) * 16;
            const uint32_t o2 = pin((aw * 2560 + ((cta >> 1) * 16 + (((cta & 1) * 16 + (ln0 & 15)) >> 2) + (ln0 >> 4) * 8) * 4 + (ln0 & 3)) * 4);
            const uint32_t ARR = sb + S_RED + ln0 * 8;
            const bool hh = ln0 >= 16;
            const uint32_t slot3 = s % 3, kvpar = (s / 3) & 1;
            const int par = s & 1, slot = s & (NSLOT - 1);
            const uint32_t ph = ((s >> 2) & 1) ^ 1;
            const uint4* src = pin_ptr(reinterpret_cast<const uint4*>(reinterpret_cast<const char*>(&g1[slot][0][0][0]) + o1));
            if (at16 == 0 && s + 1 < NSEG) {
                mbar_wait(bars + B_D1 + par * 8, (s >> 1) & 1);
                const uint32_t sl = slot3 == 2 ? 0 : slot3 + 1;
                mbar_arrive_tx(bars + B_KV + sl * 8, role == 0 ? 16384 : 8192);
                if (role != 0) {
                    const uint32_t pA = role == 0 ? 1 : 0, pB = role == 2 ? 1 : 2;
                    const uint32_t so = sb + (role == 1 ? S_KR : S_VR) + sl * 8192, bo2 = bars + B_KV + sl * 8;
                    bulk_copy_s2s(mapa_u32(so, pA), so, 8192, mapa_u32(bo2, pA));
                    bulk_copy_s2s(mapa_u32(so, pB), so, 8192, mapa_u32(bo2, pB));
                }
            }
            __syncwarp();
            bar_sync(2, 384);
            const uint32_t tb = clk32r();
            TSTAMP_AUX(8);
            const bool own = owner && s + 1 < NSEG;
            uint4 v[4];
            if (own) {
                spin_until(tb, delay1);
                TSTAMP_AUX(10);
                ld_poll4(v, src);
            }
            if (own) {
                uint32_t it = 0;
#pragma unroll 1
                while (!__all_sync(0xffffffffu, (tag_mismatch(v, ph) & 1u) == 0)) {
                    ld_poll4(v, src);
                    if (++it > WAIT_LIMIT) { g_err = 4; break; }
                }
                TSTAMP_AUX(11);
                const float a0 = (__uint_as_float(v[0].x) + __uint_as_float(v[1].x)) + (__uint_as_float(v[2].x) + __uint_as_float(v[3].x));
                const float a1 = (__uint_as_float(v[0].y) + __uint_as_float(v[1].y)) + (__uint_as_float(v[2].y) + __uint_as_float(v[3].y));
                const float a2 = (__uint_as_float(v[0].z) + __uint_as_float(v[1].z)) + (__uint_as_float(v[2].z) + __uint_as_float(v[3].z));
                const float a3 = (__uint_as_float(v[0].w) + __uint_as_float(v[1].w)) + (__uint_as_float(v[2].w) + __uint_as_float(v[3].w));
                const float k0 = (hh ? a2 : a0) + __shfl_xor_sync(0xffffffffu, hh ? a0 : a2, 16);
                const float k1 = (hh ? a3 : a1) + __shfl_xor_sync(0xffffffffu, hh ? a1 : a3, 16);
                sts64f(ARR + aw * 256, k0, k1);
                uint32_t* dstn = reinterpret_cast<uint32_t*>(reinterpret_cast<char*>(&g2[slot][0][0]) + o2);
                uint32_t* dsto = reinterpret_cast<uint32_t*>(reinterpret_cast<char*>(&g2[(s + 2) & (NSLOT - 1)][0][0]) + o2);
                bar_sync(3, 128);
                const float2 x0 = lds64f(ARR), x1 = lds64f(ARR + 256), x2 = lds64f(ARR + 512), x3 = lds64f(ARR + 768);
                uint32_t pk = pack_bf16((x0.x + x1.x) + (x2.x + x3.x), (x0.y + x1.y) + (x2.y + x3.y));
                if (pk == SENT) pk = 0x80008000u;
#pragma unroll
                for (int r = 0; r < G2R / 4; r++) st_relaxed_u32(dstn + r * 4 * 2560, pk);
#pragma unroll
                for (int r = 0; r < G2R / 4; r++) st_relaxed_u32(dsto + r * 4 * 2560, SENT);
            }
            TSTAMP_AUX(9);
            if (role == 0 && s > 0) publish_o(Og, sb, pin(at16), h, s - 1);
            if (role == 0) {
                mbar_wait(bars + B_D1 + par * 8, (s >> 1) & 1); mbar_wait(bars + B_KV + slot3 * 8, kvpar);
                const uint32_t qo = S_QKVM + par * 6144, ro = slot3 * 8192;
                bar_sync(3, 128);
                const int ln = (pin(at16) >> 4) & 31, mi = ln >> 3, row = ln & 7;
                const uint32_t A16 = sb + ln * 16;
                const uint32_t AQ = sb + (mi & 1) * 2048 + ((mi >> 1) * 8 + row) * 16;
                const uint32_t AV1 = sb + ((mi & 1) * 8 + row + 64 * (aw & 1)) * 16 + (mi >> 1) * 2048;
                const uint32_t AV2 = sb + ((mi >> 1) * 8 + row + 64 * (aw & 1)) * 16 + (mi & 1) * 2048;
                const uint32_t AO = sb + S_OST + (16 * (aw >> 1) + (ln >> 2)) * 272 + (64 * (aw & 1) + 2 * (ln & 3)) * 2;
                const uint32_t pb = s + 1 < NSEG ? bars + B_AD : 0;
                if (aw < 2) token_attn<0>(A16, AQ, AV1, AV2, AO, qo, ro, aw & 1, ln, pb, par);
                else        token_attn<1>(A16, AQ, AV1, AV2, AO, qo, ro, aw & 1, ln, pb, par);
                bar_sync(3, 128);
                TSTAMP_AUX(12);
                if (s + 1 == NSEG) publish_o(Og, sb, pin(at16), h, s);
                TSTAMP_AUX(13);
            }
        }
        cluster_sync();
    }
}

}
namespace gemm {

constexpr int BM = 128, BK = 64;
template <int BN> struct Cfg {
    static constexpr int NB = (BN + 63) / 64;
    static constexpr uint32_t A_BYTES = BM * BK * 2;
    static constexpr uint32_t B_BYTES = NB * 8192;
    static constexpr uint32_t STAGE = A_BYTES + B_BYTES;
    static constexpr int STAGES = BN == 160 ? 4 : 6;
    static constexpr uint32_t STAGING = BN == 160 ? 65536 : BM * BN * 2;
    static constexpr uint32_t S_STG = STAGES * STAGE;
    static constexpr uint32_t S_BAR = S_STG + STAGING;
    static constexpr uint32_t SMEM = S_BAR + 256;
};

template <int BN> struct Wg;
#define WG_REGS8(o) "+f"(d[o]), "+f"(d[o + 1]), "+f"(d[o + 2]), "+f"(d[o + 3]), "+f"(d[o + 4]), "+f"(d[o + 5]), "+f"(d[o + 6]), "+f"(d[o + 7])
template <> struct Wg<128> {
    static DEVI void mma(float* d, uint64_t da, uint64_t db, int scale_d) {
        asm volatile("{\n.reg .pred p;\nsetp.ne.b32 p, %66, 0;\n"
                     "wgmma.mma_async.sync.aligned.m64n128k16.f32.bf16.bf16 "
                     "{%0,%1,%2,%3,%4,%5,%6,%7,%8,%9,%10,%11,%12,%13,%14,%15,%16,%17,%18,%19,%20,%21,%22,%23,%24,%25,%26,%27,%28,%29,%30,%31,"
                     "%32,%33,%34,%35,%36,%37,%38,%39,%40,%41,%42,%43,%44,%45,%46,%47,%48,%49,%50,%51,%52,%53,%54,%55,%56,%57,%58,%59,%60,%61,%62,%63}, "
                     "%64, %65, p, 1, 1, 0, 1;\n}"
                     : WG_REGS8(0), WG_REGS8(8), WG_REGS8(16), WG_REGS8(24), WG_REGS8(32), WG_REGS8(40), WG_REGS8(48), WG_REGS8(56)
                     : "l"(da), "l"(db), "r"(scale_d));
    }
};
template <> struct Wg<160> {
    static DEVI void mma(float* d, uint64_t da, uint64_t db, int scale_d) {
        asm volatile("{\n.reg .pred p;\nsetp.ne.b32 p, %82, 0;\n"
                     "wgmma.mma_async.sync.aligned.m64n160k16.f32.bf16.bf16 "
                     "{%0,%1,%2,%3,%4,%5,%6,%7,%8,%9,%10,%11,%12,%13,%14,%15,%16,%17,%18,%19,%20,%21,%22,%23,%24,%25,%26,%27,%28,%29,%30,%31,"
                     "%32,%33,%34,%35,%36,%37,%38,%39,%40,%41,%42,%43,%44,%45,%46,%47,%48,%49,%50,%51,%52,%53,%54,%55,%56,%57,%58,%59,%60,%61,%62,%63,"
                     "%64,%65,%66,%67,%68,%69,%70,%71,%72,%73,%74,%75,%76,%77,%78,%79}, "
                     "%80, %81, p, 1, 1, 0, 1;\n}"
                     : WG_REGS8(0), WG_REGS8(8), WG_REGS8(16), WG_REGS8(24), WG_REGS8(32), WG_REGS8(40), WG_REGS8(48), WG_REGS8(56),
                       WG_REGS8(64), WG_REGS8(72)
                     : "l"(da), "l"(db), "r"(scale_d));
    }
};
template <> struct Wg<64> {
    static DEVI void mma(float* d, uint64_t da, uint64_t db, int scale_d) {
        asm volatile("{\n.reg .pred p;\nsetp.ne.b32 p, %34, 0;\n"
                     "wgmma.mma_async.sync.aligned.m64n64k16.f32.bf16.bf16 "
                     "{%0,%1,%2,%3,%4,%5,%6,%7,%8,%9,%10,%11,%12,%13,%14,%15,%16,%17,%18,%19,%20,%21,%22,%23,%24,%25,%26,%27,%28,%29,%30,%31}, "
                     "%32, %33, p, 1, 1, 0, 1;\n}"
                     : WG_REGS8(0), WG_REGS8(8), WG_REGS8(16), WG_REGS8(24)
                     : "l"(da), "l"(db), "r"(scale_d));
    }
};

__device__ __align__(128) bf16 g_Qp[32 * 2048 * 32];
__device__ __align__(128) bf16 g_Kp[32 * 2048 * 32];
__device__ __align__(128) bf16 g_Vp[32 * 2048 * 32];

constexpr float QSCALE = 0.22360679774997896f * 1.4426950408889634f;

template <int BN, int EPI>
__global__ void __launch_bounds__(288, 1)
gemm_kernel(const __grid_constant__ CUtensorMap tmA, const __grid_constant__ CUtensorMap tmB, const __grid_constant__ CUtensorMap tmC,
            const __grid_constant__ CUtensorMap tmC2, const __grid_constant__ CUtensorMap tmC3, const int nk, const int ntn, const int ntiles,
            const int col0, unsigned int* __restrict__ queue, unsigned int* __restrict__ clear) {
    using C = Cfg<BN>;
    extern __shared__ __align__(1024) uint8_t smem_raw[];
    const uint32_t sb = smem_u32(smem_raw);
    const uint32_t bars = sb + C::S_BAR;
    const uint32_t tfull = bars + 16 * C::STAGES, tempty = tfull + 16, slot = tempty + 16;
    const int tid = threadIdx.x, lane = tid & 31;
    const int warp = __shfl_sync(0xffffffffu, tid >> 5, 0);
    TL_BEGIN(EPI == 1 ? 1 : (nk == 10 ? 3 : 4));
    if (tid == 0) {
        for (int i = 0; i < C::STAGES; i++) { mbar_init(bars + 8 * i, 1); mbar_init(bars + 8 * (C::STAGES + i), 2); }
        mbar_init(tfull, 1); mbar_init(tfull + 8, 1); mbar_init(tempty, 2); mbar_init(tempty + 8, 2);
        asm volatile("fence.mbarrier_init.release.cluster;" ::: "memory");
    }
    if (clear && blockIdx.x == 0 && tid < 64) clear[tid] = 0;
    __syncthreads();
    if (warp == 8) {
        if (lane == 0) {
            int st = 0; uint32_t ph = 1;
            asm volatile("griddepcontrol.wait;" ::: "memory");
            int tile = queue ? (int)atomicAdd(queue, 1u) : (int)blockIdx.x;
            for (int it = 0;; it++) {
                const uint32_t b = it & 1;
                mbar_wait(tempty + b * 8, ((it >> 1) & 1) ^ 1);
                sts32(slot + b * 4, tile);
                mbar_arrive(tfull + b * 8);
                if (tile >= ntiles) break;
                const int tn = tile % ntn, tm = tile / ntn;
                int tnext = ntiles;
                for (int k = 0; k < nk; k++) {
                    mbar_wait(bars + 8 * (C::STAGES + st), ph);
                    mbar_arrive_tx(bars + 8 * st, C::STAGE);
                    const uint32_t base = sb + st * C::STAGE;
                    tma_load_2d(base, &tmA, k * BK, tm * BM, bars + 8 * st);
#pragma unroll
                    for (int i = 0; i < C::NB; i++) tma_load_2d(base + C::A_BYTES + i * 8192, &tmB, tn * BN + i * 64, k * BK, bars + 8 * st);
                    if (++st == C::STAGES) { st = 0; ph ^= 1; }
                    if (queue && k == nk - 3) tnext = (int)atomicAdd(queue, 1u);
                }
                tile = tnext;
            }
        }
        return;
    }
    const int wg = warp >> 2;
    int st = 0; uint32_t ph = 0;
    for (int it = 0;; it++) {
    const uint32_t tb = it & 1;
    mbar_wait(tfull + tb * 8, (it >> 1) & 1);
    int tile;
    asm volatile("ld.shared.b32 %0, [%1];" : "=r"(tile) : "r"(slot + tb * 4) : "memory");
    if (tile >= ntiles) break;
    const int tn = tile % ntn, tm = tile / ntn;
    float d[BN / 2];
    {
        int prev = -1;
        for (int k = 0; k < nk; k++) {
            mbar_wait(bars + 8 * st, ph);
            const uint32_t base = sb + st * C::STAGE;
            const uint64_t da = make_desc(base + wg * 8192, 16, 1024, 1);
            const uint64_t db = make_desc(base + C::A_BYTES, 8192, 1024, 1);
            wg_fence();
#pragma unroll
            for (int ks = 0; ks < 4; ks++) Wg<BN>::mma(d, da + (uint64_t)(ks * 2), db + (uint64_t)(ks * 128), (k | ks) != 0);
            wg_commit();
            if (prev >= 0) { wg_wait<1>(); if ((tid & 127) == 0) mbar_arrive(bars + 8 * (C::STAGES + prev)); }
            prev = st;
            if (++st == C::STAGES) { st = 0; ph ^= 1; }
        }
        wg_wait<0>();
        if ((tid & 127) == 0) { mbar_arrive(bars + 8 * (C::STAGES + prev)); mbar_arrive(tempty + tb * 8); }
#pragma unroll
        for (int i = 0; i < BN / 2; i++) asm volatile("" : "+f"(d[i]) :: "memory");
    }
    if (tid == 0) bulk_wait_read<0>();
    bar_sync(1, 256);
    const uint32_t sg = sb + C::S_STG;
    const int r0 = wg * 64 + (warp & 3) * 16 + (lane >> 2), q = lane & 3;
    if (EPI == 0) {
#pragma unroll
        for (int j = 0; j < BN / 8; j++) {
            const uint32_t box = sg + (j >> 3) * 16384, ch = j & 7;
            sts32(box + r0 * 128 + ((ch ^ (r0 & 7)) << 4) + q * 4, pack_bf16(d[4 * j], d[4 * j + 1]));
            sts32(box + (r0 + 8) * 128 + ((ch ^ (r0 & 7)) << 4) + q * 4, pack_bf16(d[4 * j + 2], d[4 * j + 3]));
        }
        fence_proxy_async();
        bar_sync(1, 256);
        if (tid == 0) {
#pragma unroll
            for (int b = 0; b < BN / 64; b++) tma_store_2d(&tmC, sg + b * 16384, col0 + tn * BN + b * 64, tm * BM);
            bulk_commit();
        }
    } else {
        const int which = tn >> 2, h0 = (tn & 3) * 8;
        const float sc = which == 0 ? QSCALE : 1.0f;
        for (int i = tid; i < 8 * 128; i += 256) {
            const int row = i & 127;
            const uint32_t rb = sg + (i >> 7) * 8192 + row * 64, sw = (row >> 1) & 3;
            asm volatile("st.shared.v2.b32 [%0], {%1,%2};" :: "r"(rb + ((2 ^ sw) << 4) + 8), "r"(which == 0 ? 0u : 0x00003F80u), "r"(0u) : "memory");
            sts128(rb + ((3 ^ sw) << 4), make_uint4(0, 0, 0, 0));
        }
        float n0[8], n1[8];
#pragma unroll
        for (int hh = 0; hh < 8; hh++) { n0[hh] = 0.f; n1[hh] = 0.f; }
#pragma unroll
        for (int j = 0; j < BN / 8; j++) {
            const int hlo = (8 * j) / 20, hhi = (8 * j + 6) / 20;
            const bool up = hlo != hhi && 8 * j + 2 * q >= 20 * hhi;
            const int hh = up ? hhi : hlo, dd = 8 * j + 2 * q - 20 * hh;
            const uint32_t p0 = pack_bf16(d[4 * j] * sc, d[4 * j + 1] * sc), p1 = pack_bf16(d[4 * j + 2] * sc, d[4 * j + 3] * sc);
            const uint32_t hb = sg + hh * 8192 + ((dd * 2) & 15);
            const uint32_t ch = dd >> 3;
            sts32(hb + r0 * 64 + ((ch ^ ((r0 >> 1) & 3)) << 4), p0);
            sts32(hb + (r0 + 8) * 64 + ((ch ^ (((r0 + 8) >> 1) & 3)) << 4), p1);
            if (which == 1) {
                const float a0 = __uint_as_float(p0 << 16), a1 = __uint_as_float(p0 & 0xFFFF0000u);
                const float b0 = __uint_as_float(p1 << 16), b1 = __uint_as_float(p1 & 0xFFFF0000u);
                const float s0 = a0 * a0 + a1 * a1, s1 = b0 * b0 + b1 * b1;
                if (hlo == hhi) { n0[hlo] += s0; n1[hlo] += s1; }
                else { n0[hlo] += up ? 0.f : s0; n1[hlo] += up ? 0.f : s1; n0[hhi] += up ? s0 : 0.f; n1[hhi] += up ? s1 : 0.f; }
            }
        }
        if (which == 1) {
#pragma unroll
            for (int hh = 0; hh < 8; hh++) {
                float a = n0[hh], b = n1[hh];
                a += __shfl_xor_sync(0xffffffffu, a, 1); b += __shfl_xor_sync(0xffffffffu, b, 1);
                a += __shfl_xor_sync(0xffffffffu, a, 2); b += __shfl_xor_sync(0xffffffffu, b, 2);
                float m = fmaxf(a, b);
                m = fmaxf(m, __shfl_xor_sync(0xffffffffu, m, 4));
                m = fmaxf(m, __shfl_xor_sync(0xffffffffu, m, 8));
                m = fmaxf(m, __shfl_xor_sync(0xffffffffu, m, 16));
                if (lane == 0) atomicMax(queue - 32 + h0 + hh, __float_as_uint(m));
            }
        }
        fence_proxy_async();
        bar_sync(1, 256);
        if (tid == 0) {
            const CUtensorMap* tc = which == 0 ? &tmC : (which == 1 ? &tmC2 : &tmC3);
#pragma unroll
            for (int hh = 0; hh < 8; hh++) tma_store_3d(tc, sg + hh * 8192, 0, tm * BM, h0 + hh);
            bulk_commit();
        }
    }
    }
    if (tid == 0) bulk_wait<0>();
    TL_END(EPI == 1 ? 1 : (nk == 10 ? 3 : 4));
}

}

namespace attn {

constexpr int S = 2048, KT = 64;
constexpr int KSTAGE = 128;
constexpr int NSTAGE = 8;
constexpr uint32_t STAGE_BYTES = KSTAGE * 64 * 2;
constexpr int NWG = 3;
constexpr uint32_t QBYTES = NWG * 4096;
constexpr uint32_t S_Q = NSTAGE * STAGE_BYTES;
constexpr uint32_t S_BAR = S_Q + 2 * QBYTES;
constexpr uint32_t SMEM = S_BAR + 256 + 128 + 16;
constexpr int TPH = 11;
constexpr int NTASK = 32 * TPH;
constexpr float BOUND_MAX = 48.0f;

__device__ __align__(128) bf16 g_Oa[2048 * 640];

#define AT_REGS8(o) "+f"(d[o]), "+f"(d[o + 1]), "+f"(d[o + 2]), "+f"(d[o + 3]), "+f"(d[o + 4]), "+f"(d[o + 5]), "+f"(d[o + 6]), "+f"(d[o + 7])
#define AT_OUT8(o) "=f"(d[o]), "=f"(d[o + 1]), "=f"(d[o + 2]), "=f"(d[o + 3]), "=f"(d[o + 4]), "=f"(d[o + 5]), "=f"(d[o + 6]), "=f"(d[o + 7])
#define AT_DESC(name, n) ".reg .b64 " name ";\nmov.b64 " name ", {%" #n ", 0x80000020};\n"
DEVI void qk_mma(float* d, uint32_t da, uint32_t db) {
    asm volatile("{\n.reg .pred p;\nsetp.ne.b32 p, 1, 0;\n" AT_DESC("dsa", 32) AT_DESC("dsb", 33)
                 "wgmma.mma_async.sync.aligned.m64n64k16.f32.bf16.bf16 "
                 "{%0,%1,%2,%3,%4,%5,%6,%7,%8,%9,%10,%11,%12,%13,%14,%15,%16,%17,%18,%19,%20,%21,%22,%23,%24,%25,%26,%27,%28,%29,%30,%31}, "
                 "dsa, dsb, p, 1, 1, 0, 0;\n}"
                 : AT_REGS8(0), AT_REGS8(8), AT_REGS8(16), AT_REGS8(24)
                 : "r"(da), "r"(db));
}
DEVI void qk_mma0(float* d, uint32_t da, uint32_t db) {
    asm volatile("{\n.reg .pred p;\nsetp.ne.b32 p, 0, 0;\n" AT_DESC("dsa", 32) AT_DESC("dsb", 33)
                 "wgmma.mma_async.sync.aligned.m64n64k16.f32.bf16.bf16 "
                 "{%0,%1,%2,%3,%4,%5,%6,%7,%8,%9,%10,%11,%12,%13,%14,%15,%16,%17,%18,%19,%20,%21,%22,%23,%24,%25,%26,%27,%28,%29,%30,%31}, "
                 "dsa, dsb, p, 1, 1, 0, 0;\n}"
                 : AT_OUT8(0), AT_OUT8(8), AT_OUT8(16), AT_OUT8(24)
                 : "r"(da), "r"(db));
}
DEVI void pv_mma(float* d, const uint32_t* a, uint32_t db) {
    asm volatile("{\n.reg .pred p;\nsetp.ne.b32 p, 1, 0;\n" AT_DESC("dsc", 16)
                 "wgmma.mma_async.sync.aligned.m64n24k16.f32.bf16.bf16 "
                 "{%0,%1,%2,%3,%4,%5,%6,%7,%8,%9,%10,%11}, {%12,%13,%14,%15}, dsc, p, 1, 1, 1;\n}"
                 : AT_REGS8(0), "+f"(d[8]), "+f"(d[9]), "+f"(d[10]), "+f"(d[11])
                 : "r"(a[0]), "r"(a[1]), "r"(a[2]), "r"(a[3]), "r"(db));
}

DEVI float ex2_poly(float x) {
    const float t = x + 12582912.0f;
    const float r = x - (t - 12582912.0f);
    float p = fmaf(r, 0.009618129f, 0.055504109f);
    p = fmaf(p, r, 0.240226507f);
    p = fmaf(p, r, 0.693147181f);
    p = fmaf(p, r, 1.0f);
    return __uint_as_float(__float_as_uint(p) + (__float_as_uint(t) << 23));
}

#define POLY_MASK 0x21

DEVI float ex2v(float x) { float y; asm volatile("ex2.approx.ftz.f32 %0, %1;" : "=f"(y) : "f"(x)); return y; }
template <bool SAFE>
DEVI void exp_tile(float (&s)[KT / 2], uint32_t (&p)[KT / 4], float (&o)[12], float& m0, float& m1) {
    if (!SAFE) {
        float x0 = m0, x1 = m1;
#pragma unroll
        for (int j = 0; j < KT / 8; j++) { x0 = fmaxf(x0, fmaxf(s[4 * j], s[4 * j + 1])); x1 = fmaxf(x1, fmaxf(s[4 * j + 2], s[4 * j + 3])); }
        x0 = fmaxf(x0, __shfl_xor_sync(0xffffffffu, x0, 1)); x1 = fmaxf(x1, __shfl_xor_sync(0xffffffffu, x1, 1));
        x0 = fmaxf(x0, __shfl_xor_sync(0xffffffffu, x0, 2)); x1 = fmaxf(x1, __shfl_xor_sync(0xffffffffu, x1, 2));
        const float c0 = ex2(m0 - x0), c1 = ex2(m1 - x1);
        m0 = x0; m1 = x1;
#pragma unroll
        for (int j = 0; j < 3; j++) { o[4 * j] *= c0; o[4 * j + 1] *= c0; o[4 * j + 2] *= c1; o[4 * j + 3] *= c1; }
#pragma unroll
        for (int j = 0; j < KT / 8; j++) { s[4 * j] -= m0; s[4 * j + 1] -= m0; s[4 * j + 2] -= m1; s[4 * j + 3] -= m1; }
    }
#pragma unroll
    for (int i = 0; i < KT / 4; i++) {
        const int e0 = 2 * i, e1 = 2 * i + 1;
        const float a = (SAFE && ((POLY_MASK >> (e0 & 7)) & 1)) ? ex2_poly(s[e0]) : ex2v(s[e0]);
        const float b = (SAFE && ((POLY_MASK >> (e1 & 7)) & 1)) ? ex2_poly(s[e1]) : ex2v(s[e1]);
        p[i] = pack_bf16(a, b);
    }
}
template <int N> DEVI void keep(float (&x)[N]) {
#pragma unroll
    for (int i = 0; i < N; i++) asm volatile("" : "+f"(x[i]) :: "memory");
}

template <bool SAFE>
DEVI void attn_loop(const uint32_t dq, float (&o)[12], uint32_t sb, uint32_t bars, int tid, int g0) {
    constexpr int TPS = KSTAGE / KT, NS = S / KSTAGE;
    float m0 = -INFINITY, m1 = -INFINITY;
    float sA[KT / 2], sB[KT / 2];
    uint32_t p[KT / 4];
    const uint32_t dk0 = (uint32_t)make_desc(sb, 16, 512, 2), dv0 = (uint32_t)make_desc(sb + KSTAGE * 64, 512, 512, 2);
    auto issue_qk = [&](float (&s)[KT / 2], uint32_t off) {
        const uint32_t dk = dk0 + off;
        wg_fence();
        qk_mma0(s, dq, dk);
        qk_mma(s, dq + 2, dk + 2);
        wg_commit();
    };
    auto issue_pv = [&](uint32_t off) {
        const uint32_t dv = dv0 + off;
        wg_fence();
#pragma unroll
        for (int ks = 0; ks < KT / 16; ks++) pv_mma(o, &p[4 * ks], dv + ks * 64);
        wg_commit();
    };
    auto release = [&](int st) { if ((tid & 127) == 0) mbar_arrive(bars + 8 * (NSTAGE + st)); };
    constexpr uint32_t TOFF = KT * 64 >> 4, SOFF = STAGE_BYTES >> 4;
    keep(o);
    int st = g0 % NSTAGE; uint32_t ph = (g0 / NSTAGE) & 1;
    if (!SAFE) {
#pragma unroll 1
        for (int kb = 0; kb < NS; kb++) {
            mbar_wait(bars + 8 * st, ph);
#pragma unroll 1
            for (int t = 0; t < TPS; t++) {
                issue_qk(sA, st * SOFF + t * TOFF);
                wg_wait<0>();
                keep(sA);
                exp_tile<false>(sA, p, o, m0, m1);
                issue_pv(st * SOFF + t * TOFF);
                wg_wait<0>();
                keep(o);
            }
            release(st);
            if (++st == NSTAGE) { st = 0; ph ^= 1; }
        }
        return;
    }
    static_assert(TPS == 2 && NSTAGE % 2 == 0, "body below is written for two tiles per stage");
    mbar_wait(bars + 8 * st, ph);
    issue_qk(sA, st * SOFF);
    wg_wait<0>();
    keep(sA);
#pragma unroll 1
    for (int kb = 0; kb < NS; kb += 2) {
        const uint32_t so = __shfl_sync(0xffffffffu, st * SOFF, 0);
        const int stn = st == NSTAGE - 2 ? 0 : st + 2;
        const uint32_t phn = st == NSTAGE - 2 ? ph ^ 1 : ph;
        bool okn = false;
#pragma unroll
        for (int t = 0; t < 4; t++) {
            float (&sc)[KT / 2] = (t & 1) ? sB : sA;
            float (&sn)[KT / 2] = (t & 1) ? sA : sB;
            const uint32_t coff = so + (t >> 1) * SOFF + (t & 1) * TOFF;
            uint32_t noff = so + ((t + 1) >> 1) * SOFF + ((t + 1) & 1) * TOFF;
            if (t == 1 && !okn) mbar_wait(bars + 8 * (st + 1), ph);
            if (t == 3) {
                if (kb + 2 < NS) { if (!okn) mbar_wait(bars + 8 * stn, phn); noff = stn * SOFF; } else noff = coff;
            }
            if (t == 0) okn = mbar_test(bars + 8 * (st + 1), ph);
            if (t == 2) okn = mbar_test(bars + 8 * stn, phn);
            issue_qk(sn, noff);
            wg_wait<1>();
            keep(sc);
            if (t == 2) release(st);
            exp_tile<true>(sc, p, o, m0, m1);
            issue_pv(coff);
        }
        wg_wait<0>();
        keep(sA);
        release(st + 1);
        st = stn; ph = phn;
    }
    keep(o);
}

__global__ void __launch_bounds__(NWG * 128 + 128, 1)
attn_kernel(const __grid_constant__ CUtensorMap tmK, const __grid_constant__ CUtensorMap tmV, const __grid_constant__ CUtensorMap tmQ,
            const unsigned int* __restrict__ kmax2, unsigned int* __restrict__ queue) {
    extern __shared__ __align__(1024) uint8_t smem_raw[];
    const uint32_t sb = smem_u32(smem_raw);
    const uint32_t bars = sb + S_BAR;
    const uint32_t qfull = bars + 16 * NSTAGE, qempty = qfull + 16, kmx = bars + 256, slot = bars + 384;
    const int tid = threadIdx.x, lane = tid & 31;
    const int warp = __shfl_sync(0xffffffffu, tid >> 5, 0);
    TL_BEGIN(2);
    if (tid == 0) {
        for (int i = 0; i < NSTAGE; i++) { mbar_init(bars + 8 * i, 1); mbar_init(bars + 8 * (NSTAGE + i), NWG); }
        mbar_init(qfull, 1); mbar_init(qfull + 8, 1); mbar_init(qempty, NWG); mbar_init(qempty + 8, NWG);
        asm volatile("fence.mbarrier_init.release.cluster;" ::: "memory");
    }
    if (tid >= 32 && tid < 64) sts32(kmx + (tid - 32) * 4, kmax2[tid - 32]);
    __syncthreads();
    if (warp >= NWG * 4) {
        asm volatile("setmaxnreg.dec.sync.aligned.u32 40;");
        if (tid == NWG * 128) {
            int st = 0; uint32_t ph = 1;
            int task = (int)atomicAdd(queue, 1u);
            for (int it = 0;; it++) {
                const uint32_t b = it & 1;
                mbar_wait(qempty + b * 8, ((it >> 1) & 1) ^ 1);
                sts32(slot + b * 4, task);
                if (task >= NTASK) { mbar_arrive(qfull + b * 8); break; }
                const int h = task / TPH, rt0 = (task - h * TPH) * NWG;
                mbar_arrive_tx(qfull + b * 8, QBYTES);
                for (int w = 0; w < NWG; w++)
                    tma_load_3d(sb + S_Q + b * QBYTES + w * 4096, &tmQ, 0, min(rt0 + w, 31) * 64, h, qfull + b * 8);
                int tnext = NTASK;
                for (int kb = 0; kb < S / KSTAGE; kb++) {
                    mbar_wait(bars + 8 * (NSTAGE + st), ph);
                    mbar_arrive_tx(bars + 8 * st, STAGE_BYTES);
                    tma_load_3d(sb + st * STAGE_BYTES, &tmK, 0, kb * KSTAGE, h, bars + 8 * st);
                    tma_load_3d(sb + st * STAGE_BYTES + KSTAGE * 64, &tmV, 0, kb * KSTAGE, h, bars + 8 * st);
                    if (++st == NSTAGE) { st = 0; ph ^= 1; }
                    if (kb == S / KSTAGE - NSTAGE - 2) tnext = (int)atomicAdd(queue, 1u);
                }
                task = tnext;
            }
        }
        return;
    }
    asm volatile("setmaxnreg.inc.sync.aligned.u32 152;");
    const int q = lane & 3, wg = warp >> 2, rl = (warp & 3) * 16 + (lane >> 2);
    for (int it = 0;; it++) {
        const uint32_t b = it & 1, qb = sb + S_Q + b * QBYTES + wg * 4096;
        mbar_wait(qfull + b * 8, (it >> 1) & 1);
        int task;
        asm volatile("ld.shared.b32 %0, [%1];" : "=r"(task) : "r"(slot + b * 4) : "memory");
        if (task >= NTASK) { TL_END(2); break; }
        const int h = task / TPH, rt = (task - h * TPH) * NWG + wg;
        if (rt >= 32) {
            int g = it * (S / KSTAGE);
            for (int kb = 0; kb < S / KSTAGE; kb++, g++) {
                mbar_wait(bars + 8 * (g % NSTAGE), (g / NSTAGE) & 1);
                if ((tid & 127) == 0) mbar_arrive(bars + 8 * (NSTAGE + g % NSTAGE));
            }
            if ((tid & 127) == 0) mbar_arrive(qempty + b * 8);
            continue;
        }
        float km2;
        asm volatile("ld.shared.f32 %0, [%1];" : "=f"(km2) : "r"(kmx + h * 4) : "memory");
        const uint32_t a0 = qb + rl * 64 + q * 4, sw = (rl >> 1) & 3;
        float n0 = 0.f, n1 = 0.f;
#pragma unroll
        for (int c = 0; c < 3; c++) {
            uint32_t w0, w1;
            asm volatile("ld.shared.b32 %0, [%1];" : "=r"(w0) : "r"(a0 + ((c ^ sw) << 4)) : "memory");
            asm volatile("ld.shared.b32 %0, [%1];" : "=r"(w1) : "r"(a0 + 512 + ((c ^ sw) << 4)) : "memory");
            const float l0 = __uint_as_float(w0 << 16), h0 = __uint_as_float(w0 & 0xFFFF0000u);
            const float l1 = __uint_as_float(w1 << 16), h1 = __uint_as_float(w1 & 0xFFFF0000u);
            n0 += l0 * l0 + h0 * h0; n1 += l1 * l1 + h1 * h1;
        }
        n0 += __shfl_xor_sync(0xffffffffu, n0, 1); n1 += __shfl_xor_sync(0xffffffffu, n1, 1);
        n0 += __shfl_xor_sync(0xffffffffu, n0, 2); n1 += __shfl_xor_sync(0xffffffffu, n1, 2);
        const float b0 = sqrtf(n0 * km2) * 1.01f + 1e-3f, b1 = sqrtf(n1 * km2) * 1.01f + 1e-3f;
        const bool ok = b0 <= BOUND_MAX && b1 <= BOUND_MAX;
        uint32_t allok;
        asm volatile("{\n.reg .pred p, r;\nsetp.ne.b32 p, %1, 0;\nbar.red.and.pred r, %2, 128, p;\nselp.u32 %0, 1, 0, r;\n}"
                     : "=r"(allok) : "r"((uint32_t)ok), "r"(1 + wg) : "memory");
        if (allok && q == 2) { sts32(a0 + ((2 ^ sw) << 4), pack_bf16(-b0, 0.f)); sts32(a0 + 512 + ((2 ^ sw) << 4), pack_bf16(-b1, 0.f)); }
        fence_proxy_async();
        bar_sync(1 + wg, 128);
        const uint32_t dq = (uint32_t)make_desc(qb, 16, 512, 2);
        float o[12];
#pragma unroll
        for (int i = 0; i < 12; i++) o[i] = 0.f;
        if (allok) attn_loop<true>(dq, o, sb, bars, tid, it * (S / KSTAGE));
        else       attn_loop<false>(dq, o, sb, bars, tid, it * (S / KSTAGE));
        if ((tid & 127) == 0) mbar_arrive(qempty + b * 8);
        const float l0 = __shfl_sync(0xffffffffu, o[8], (lane & ~3) | 2), l1 = __shfl_sync(0xffffffffu, o[10], (lane & ~3) | 2);
        const float i0 = 1.0f / l0, i1 = 1.0f / l1;
        uint32_t* d0 = reinterpret_cast<uint32_t*>(g_Oa + (size_t)(rt * 64 + rl) * 640 + h * 20);
        uint32_t* d1 = d0 + 8 * 320;
        d0[q] = pack_bf16(o[0] * i0, o[1] * i0);         d1[q] = pack_bf16(o[2] * i1, o[3] * i1);
        d0[q + 4] = pack_bf16(o[4] * i0, o[5] * i0);     d1[q + 4] = pack_bf16(o[6] * i1, o[7] * i1);
        if (q < 2) { d0[q + 8] = pack_bf16(o[8] * i0, o[9] * i0); d1[q + 8] = pack_bf16(o[10] * i1, o[11] * i1); }
    }
}

}
typedef CUresult (*PFN_encodeTiled)(CUtensorMap*, CUtensorMapDataType, cuuint32_t, void*, const cuuint64_t*, const cuuint64_t*,
                                    const cuuint32_t*, const cuuint32_t*, CUtensorMapInterleave, CUtensorMapSwizzle,
                                    CUtensorMapL2promotion, CUtensorMapFloatOOBfill);
static PFN_encodeTiled get_encode() {
    static PFN_encodeTiled fn = nullptr;
    if (!fn) {
        void* p = nullptr; cudaDriverEntryPointQueryResult q;
        cudaGetDriverEntryPoint("cuTensorMapEncodeTiled", &p, cudaEnableDefault, &q);
        fn = (PFN_encodeTiled)p;
    }
    return fn;
}
static CUtensorMap make_tmap(const void* base, int rank, const uint64_t* dims, const uint64_t* strides_bytes, const uint32_t* box,
                             CUtensorMapSwizzle swz) {
    CUtensorMap m;
    cuuint64_t d[5], st[5]; cuuint32_t b[5], es[5];
    for (int i = 0; i < rank; i++) { d[i] = dims[i]; b[i] = box[i]; es[i] = 1; }
    for (int i = 0; i + 1 < rank; i++) st[i] = strides_bytes[i];
    CUresult r = get_encode()(&m, CU_TENSOR_MAP_DATA_TYPE_BFLOAT16, rank, (void*)base, d, st, b, es, CU_TENSOR_MAP_INTERLEAVE_NONE, swz,
                              CU_TENSOR_MAP_L2_PROMOTION_L2_128B, CU_TENSOR_MAP_FLOAT_OOB_FILL_NONE);
    if (r != CUDA_SUCCESS) fprintf(stderr, "cuTensorMapEncodeTiled failed: %d\n", (int)r);
    return m;
}
__device__ __align__(128) bf16 g_Ob[2048 * 4096];

__device__ unsigned int g_ctl[64];

struct Plan {
    CUtensorMap aX, aWqkv, aQp, aKp, aVp, aKld, aVld, aQld, aO, aWo, outA;
    CUtensorMap bWq, bWk, bWv, bWoC, bX, bO, bWoG;
    void *pQp, *pOb, *pCtl;
    const void* in[9]; void* out;
    int prioHi;
    bool ready;
};

static void build_plan(Plan& P, void* const* d_in, void* d_out) {
    void *Qp, *Kp, *Vp, *Oa, *Ob;
    cudaGetSymbolAddress(&Qp, gemm::g_Qp); cudaGetSymbolAddress(&Kp, gemm::g_Kp); cudaGetSymbolAddress(&Vp, gemm::g_Vp);
    cudaGetSymbolAddress(&Oa, attn::g_Oa); cudaGetSymbolAddress(&Ob, g_Ob);
    P.pQp = Qp; P.pOb = Ob;
    cudaGetSymbolAddress(&P.pCtl, g_ctl);
    const CUtensorMapSwizzle S128 = CU_TENSOR_MAP_SWIZZLE_128B, S64 = CU_TENSOR_MAP_SWIZZLE_64B;
    { uint64_t d[2] = {640, 2048}, s[1] = {1280}; uint32_t b[2] = {64, 128}; P.aX = make_tmap(d_in[0], 2, d, s, b, S128); P.aO = make_tmap(Oa, 2, d, s, b, S128); }
    { uint64_t d[2] = {1920, 640}, s[1] = {3840}; uint32_t b[2] = {64, 64}; P.aWqkv = make_tmap(d_in[1], 2, d, s, b, S128); }
    { uint64_t d[2] = {640, 640}, s[1] = {1280}; uint32_t b[2] = {64, 64}; P.aWo = make_tmap(d_in[2], 2, d, s, b, S128); }
    { uint64_t d[3] = {32, 2048, 32}, s[2] = {64, 2048 * 64}; uint32_t b[3] = {32, 128, 1}, b2[3] = {32, (uint32_t)attn::KSTAGE, 1};
      P.aQp = make_tmap(Qp, 3, d, s, b, S64); P.aKp = make_tmap(Kp, 3, d, s, b, S64); P.aVp = make_tmap(Vp, 3, d, s, b, S64);
      uint32_t b3[3] = {32, 64, 1}; P.aQld = make_tmap(Qp, 3, d, s, b3, S64);
      P.aKld = make_tmap(Kp, 3, d, s, b2, S64); P.aVld = make_tmap(Vp, 3, d, s, b2, S64); }
    { uint64_t d[2] = {1280, 2048}, s[1] = {2560}; uint32_t b[2] = {64, 128}; P.outA = make_tmap(d_out, 2, d, s, b, S128); }
    { uint64_t d[2] = {4096, 640}, s[1] = {8192}; uint32_t b[2] = {64, 128};
      P.bWq = make_tmap(d_in[5], 2, d, s, b, S128); P.bWk = make_tmap(d_in[6], 2, d, s, b, S128); P.bWv = make_tmap(d_in[7], 2, d, s, b, S128); }
    { uint64_t d[2] = {640, 4096}, s[1] = {1280}; uint32_t b[2] = {64, 128}, b2[2] = {64, 64};
      P.bWoC = make_tmap(d_in[8], 2, d, s, b, S128); P.bWoG = make_tmap(d_in[8], 2, d, s, b2, S128); }
    { uint64_t d[3] = {64, 2048, 10}, s[2] = {1280, 128}; uint32_t b[3] = {64, 32, 10}; P.bX = make_tmap(d_in[3], 3, d, s, b, S128); }
    { uint64_t d[2] = {4096, 2048}, s[1] = {8192}; uint32_t b[2] = {64, 128}; P.bO = make_tmap(Ob, 2, d, s, b, S128); }
    { int lo = 0, hi = 0; cudaDeviceGetStreamPriorityRange(&lo, &hi); P.prioHi = hi; }
    cudaFuncSetAttribute(gemm::gemm_kernel<160, 1>, cudaFuncAttributeMaxDynamicSharedMemorySize, gemm::Cfg<160>::SMEM);
    cudaFuncSetAttribute(gemm::gemm_kernel<128, 0>, cudaFuncAttributeMaxDynamicSharedMemorySize, gemm::Cfg<128>::SMEM);
    cudaFuncSetAttribute(attn::attn_kernel, cudaFuncAttributeMaxDynamicSharedMemorySize, attn::SMEM);
    cudaFuncSetAttribute(chain::chain_kernel, cudaFuncAttributeMaxDynamicSharedMemorySize, chain::SMEM_BYTES);
}

#define ATTN_GRID 132
#define DELAY1 250
#define DELAY2 1900

extern "C" void kernel_launch(void* const* d_in, const int* in_sizes, int n_in, void* d_out, int out_size) {
    static Plan P;
    static cudaStream_t s2 = nullptr;
    static cudaEvent_t evFork = nullptr, evJoin = nullptr;
    bool same = P.ready && P.out == d_out;
    for (int i = 0; i < 9 && same; i++) same = P.in[i] == d_in[i];
    if (!same) {
        build_plan(P, d_in, d_out);
        for (int i = 0; i < 9; i++) P.in[i] = d_in[i];
        P.out = d_out; P.ready = true;
    }
    if (!s2) {
        cudaStreamCreateWithFlags(&s2, cudaStreamNonBlocking);
        cudaEventCreateWithFlags(&evFork, cudaEventDisableTiming);
        cudaEventCreateWithFlags(&evJoin, cudaEventDisableTiming);
    }
    cudaStream_t s1 = cudaStreamPerThread;
    unsigned int* ctl = (unsigned int*)P.pCtl;
    cudaEventRecord(evFork, s1);
    cudaStreamWaitEvent(s2, evFork, 0);
    {
        cudaLaunchConfig_t cfg = {};
        cfg.gridDim = dim3(chain::NCTA); cfg.blockDim = dim3(384); cfg.dynamicSmemBytes = chain::SMEM_BYTES; cfg.stream = s1;
        cudaLaunchAttribute at[2];
        at[0].id = cudaLaunchAttributeClusterDimension; at[0].val.clusterDim.x = 3; at[0].val.clusterDim.y = 1; at[0].val.clusterDim.z = 1;
        at[1].id = cudaLaunchAttributePriority; at[1].val.priority = P.prioHi;
        cfg.attrs = at; cfg.numAttrs = 2;
        cudaLaunchKernelEx(&cfg, chain::chain_kernel, P.bWq, P.bWk, P.bWv, P.bWoC, P.bX, (const bf16*)d_in[4], (bf16*)P.pOb,
                           (uint32_t)DELAY1, (uint32_t)DELAY2);
    }
    {
        cudaLaunchConfig_t cfg = {};
        cfg.gridDim = dim3(80); cfg.blockDim = dim3(288); cfg.dynamicSmemBytes = gemm::Cfg<128>::SMEM; cfg.stream = s1;
        cudaLaunchAttribute at[2];
        at[0].id = cudaLaunchAttributePriority; at[0].val.priority = P.prioHi;
        at[1].id = cudaLaunchAttributeProgrammaticStreamSerialization; at[1].val.programmaticStreamSerializationAllowed = 1;
        cfg.attrs = at; cfg.numAttrs = 2;
        cudaLaunchKernelEx(&cfg, gemm::gemm_kernel<128, 0>, P.bO, P.bWoG, P.outA, P.outA, P.outA, 64, 5, 80, 640, (unsigned int*)nullptr, (unsigned int*)nullptr);
    }
    gemm::gemm_kernel<160, 1><<<132, 288, gemm::Cfg<160>::SMEM, s2>>>(P.aX, P.aWqkv, P.aQp, P.aKp, P.aVp, 10, 12, 192, 0, ctl + 32, (unsigned int*)nullptr);
    attn::attn_kernel<<<ATTN_GRID, attn::NWG * 128 + 128, attn::SMEM, s2>>>(P.aKld, P.aVld, P.aQld, ctl, ctl + 33);
    gemm::gemm_kernel<128, 0><<<80, 288, gemm::Cfg<128>::SMEM, s2>>>(P.aO, P.aWo, P.outA, P.outA, P.outA, 10, 5, 80, 0, (unsigned int*)nullptr, ctl);
    cudaEventRecord(evJoin, s2);
    cudaStreamWaitEvent(s1, evJoin, 0);
}
```
